```python
import torch

def _softmax(x, axis=-1):
    return torch.softmax(x, dim=axis)
def _gelu(x):
    return torch.nn.functional.gelu(x, approximate="tanh")
def _silu(x):
    return torch.nn.functional.silu(x)
def _sigmoid(x):
    return torch.sigmoid(x)
def _layernorm(x, axis=-1, eps=1e-5):
    m = x.mean(dim=axis, keepdim=True)
    v = x.var(dim=axis, keepdim=True, unbiased=False)
    return (x - m) / torch.sqrt(v + eps)
def _scatter_add(tgt, idx, src, axis=0):
    return tgt.clone().index_add_(axis, idx, src)
def _segment_sum(src, seg, n):
    out = torch.zeros((n,) + src.shape[1:], dtype=src.dtype)
    return out.index_add_(0, seg, src)
def _pad(x, pw):
    flat = tuple(v for pair in reversed(pw) for v in pair)
    return torch.nn.functional.pad(x, flat)

kernel_name = 'parallel_sum__ssm_conv_s4d__geglu_ffn__prompt'

def setup_inputs():

    _w = (lambda a: (lambda t: t.to(torch.bfloat16) if t.is_floating_point() else t)(torch.as_tensor(a)))
    def _A_setup():
        Bsz, L, D, N = 1, 2048, 512, 128
        return {
            "u": _w((lambda *s: torch.randn(*s, dtype=torch.bfloat16) * 0.05)(Bsz, L, D)),
            "log_A_real": _w((lambda *s: torch.randn(*s, dtype=torch.bfloat16) * 3.2)(D, N) * 0.5),
            "A_imag": _w((lambda *s: torch.randn(*s, dtype=torch.bfloat16) * 0.1)(D, N) * 3.14),
            "C_real": _w((lambda *s: torch.randn(*s, dtype=torch.bfloat16) * 1.6)(D, N) / N ** 0.5),
            "C_imag": _w((lambda *s: torch.randn(*s, dtype=torch.bfloat16) * 1.6)(D, N) / N ** 0.5),
            "log_dt": _w((lambda *s: torch.randn(*s, dtype=torch.bfloat16) * 0.1)(D) * 0.5 - 4.0),
            "D_skip": _w((lambda *s: torch.randn(*s, dtype=torch.bfloat16) * 0.2)(D)),
        }
    _A_in = _A_setup()

    def _B_setup():
        B, S, D, F = 1, 2048, 512, 1792
        return {
            "x": _w((lambda *s: torch.randn(*s, dtype=torch.bfloat16) * 0.05)(B, S, D)),
            "w_gate": _w((lambda *s: torch.randn(*s, dtype=torch.bfloat16) * 0.05)(D, F)),
            "w_up": _w((lambda *s: torch.randn(*s, dtype=torch.bfloat16) * 0.05)(D, F)),
            "w_down": _w((lambda *s: torch.randn(*s, dtype=torch.bfloat16) * 0.05)(F, D)),
        }
    _B_in = _B_setup()

    return {
        "A_u": _A_in["u"],
        "A_log_A_real": _A_in["log_A_real"],
        "A_A_imag": _A_in["A_imag"],
        "A_C_real": _A_in["C_real"],
        "A_C_imag": _A_in["C_imag"],
        "A_log_dt": _A_in["log_dt"],
        "A_D_skip": _A_in["D_skip"],
        "B_x": _B_in["x"],
        "B_w_gate": _B_in["w_gate"],
        "B_w_up": _B_in["w_up"],
        "B_w_down": _B_in["w_down"],
    }

def reference(A_u, A_log_A_real, A_A_imag, A_C_real, A_C_imag, A_log_dt, A_D_skip, B_x, B_w_gate, B_w_up, B_w_down):
    def _A_ref(u, log_A_real, A_imag, C_real, C_imag, log_dt, D_skip):
        L = u.shape[1]
        dt = torch.exp(log_dt)
        A = -torch.exp(log_A_real) + 1j * A_imag
        C = (C_real + 1j * C_imag) * dt[:, None]
        pos = (lambda x, dt: x.to(dt))(torch.arange(L), log_dt.dtype)
        P = torch.exp((A * dt[:, None])[:, :, None] * pos[None, None, :])
        K = 2.0 * torch.einsum("dn,dnl->dl", C, P).real
        L2 = 2 * L
        u_t = (lambda x, *d: x.permute(*d))(u, 0, 2, 1)
        Kf = (lambda x, *a, **k: torch.fft.rfft(x.float(), *a, **k))(K, L2)
        Uf = (lambda x, *a, **k: torch.fft.rfft(x.float(), *a, **k))(u_t, L2)
        y = (lambda x, *a, **k: torch.fft.irfft(x, *a, **k).to(torch.bfloat16))(Uf * Kf[None, :, :], L2)[:, :, :L]
        y = (lambda x, *d: x.permute(*d))(y, 0, 2, 1)
        return y + u * D_skip[None, None, :]

    def _B_ref(x, w_gate, w_up, w_down):
        return (_gelu(x @ w_gate) * (x @ w_up)) @ w_down

    x = A_u
    xn = _layernorm(x, axis=-1)
    return x + _A_ref(xn, A_log_A_real, A_A_imag, A_C_real, A_C_imag, A_log_dt, A_D_skip) + _B_ref(xn, B_w_gate, B_w_up, B_w_down)
```

```cpp
#include <cuda_runtime.h>
#include <cuda_bf16.h>
#include <cuda.h>
#include <stdint.h>

namespace {

constexpr int kL = 2048, kD = 512, kF = 1792, kN = 128;

__device__ __align__(16) float2 g_stat[kL];
__device__ __align__(16) float g_S[16 * 8 * 448];
__device__ __align__(1024) __nv_bfloat16 g_xnT[kD * kL];
__device__ __align__(1024) __nv_bfloat16 g_h[16 * 224 * 128 * 8];
__device__ __align__(1024) __nv_bfloat16 g_y[kL * kD];
__device__ unsigned g_epoch, g_done, g_xn_all;
__device__ unsigned g_s_cnt[8];
__device__ unsigned g_xn_cnt[16];
__device__ unsigned g_h_cnt[16 * 8 * 2];
__device__ unsigned g_y_cnt[8];

#define TS(i) do { } while (0)
constexpr int SM_XN = 0;
constexpr int SM_W = 131072;
constexpr int W_STAGES = 4, W_STAGE_BYTES = 16384;
constexpr int G2_STAGES = 4, G2_STAGE_BYTES = 32768;
constexpr int SM_CV_RED = SM_W;
constexpr int TBL_COPY = 4160, TBL_BYTES = 8320;
constexpr int SM_CV_TBL3 = SM_W + 32768;
constexpr int SM_CV_U = SM_W + 41984;
constexpr int U_PAD = 56, U_BYTES = (128 + U_PAD) * 128;
constexpr int SM_CV_TBL12 = SM_W + 65536;
constexpr int SM_KD = SM_CV_TBL12 + 2 * TBL_BYTES;
constexpr int KD_STRIDE = 648;
constexpr int SM_KC = SM_KD + 4 * KD_STRIDE * 2;
constexpr int SM_CV_TBL0 = SM_KC;
constexpr int SM_STAT = SM_KC + 4 * 32 * 80;
constexpr int SM_S = SM_STAT + 1024;
constexpr int SM_LNS = SM_S + 1792;
constexpr int SM_BAR = SM_LNS + 128;
constexpr int SM_TOTAL = SM_BAR + 320;
constexpr int SMEM_BYTES = 232448;

constexpr int SM_KCC = SM_XN + 81920;
constexpr int SM_KPART = SM_XN + 97280;
constexpr int B_WFULL = 0, B_WEMPTY = 5, B_GFULL = 10, B_GEMPTY = 14, B_P1DONE = 18, B_UFULL = 19  ,
              B_PEERRDY = 21, B_REDFULL = 22, B_EPIRDY = 23, B_XFULL = 24  , B_KGDONE = 32, B_SCRFREE = 33;

__device__ __forceinline__ uint32_t s2u(const void* p) { return (uint32_t)__cvta_generic_to_shared(p); }
__device__ __forceinline__ void mbar_init(uint32_t a, int c) { asm volatile("mbarrier.init.shared::cta.b64 [%0], %1;" ::"r"(a), "r"(c)); }
__device__ __forceinline__ void mbar_expect(uint32_t a, uint32_t b) { asm volatile("mbarrier.arrive.expect_tx.shared::cta.b64 _, [%0], %1;" ::"r"(a), "r"(b) : "memory"); }
__device__ __forceinline__ void mbar_arrive(uint32_t a) { asm volatile("mbarrier.arrive.shared::cta.b64 _, [%0];" ::"r"(a) : "memory"); }
__device__ __forceinline__ void mbar_arrive_remote(uint32_t a, uint32_t cta) {
  asm volatile("{\n.reg .b32 ra;\nmapa.shared::cluster.u32 ra, %0, %1;\nmbarrier.arrive.shared::cluster.b64 _, [ra];\n}\n" ::"r"(a), "r"(cta) : "memory");
}
__device__ __forceinline__ void mbar_wait(uint32_t a, uint32_t ph) {
  uint32_t ok; int n = 0;
  while (true) {
    asm volatile("{\n.reg .pred p;\nmbarrier.try_wait.parity.shared::cta.b64 p, [%1], %2;\nselp.u32 %0,1,0,p;\n}\n" : "=r"(ok) : "r"(a), "r"(ph) : "memory");
    if (ok) break;
    if (++n > (1 << 22)) break;
  }
}
__device__ __forceinline__ void mbar_wait_cluster(uint32_t a, uint32_t ph) {
  uint32_t ok; int n = 0;
  while (true) {
    asm volatile("{\n.reg .pred p;\nmbarrier.try_wait.parity.acquire.cluster.shared::cta.b64 p, [%1], %2;\nselp.u32 %0,1,0,p;\n}\n" : "=r"(ok) : "r"(a), "r"(ph) : "memory");
    if (ok) break;
    if (++n > (1 << 22)) break;
  }
}
__device__ __forceinline__ unsigned ld_acquire(const unsigned* p) {
  unsigned v; asm volatile("ld.acquire.gpu.global.u32 %0, [%1];" : "=r"(v) : "l"(p) : "memory"); return v;
}
__device__ __forceinline__ void flag_wait(const unsigned* p, unsigned target) {
  int n = 0;
  while ((int)(ld_acquire(p) - target) < 0) { if (++n > (1 << 24)) break; __nanosleep(64); }
}
__device__ __forceinline__ void fence_gpu() { asm volatile("fence.acq_rel.gpu;" ::: "memory"); }
__device__ __forceinline__ void fence_proxy_async() { asm volatile("fence.proxy.async.global;" ::: "memory"); }
__device__ __forceinline__ void fence_proxy_smem() { asm volatile("fence.proxy.async.shared::cta;" ::: "memory"); }
__device__ __forceinline__ void bar_sync(int id, int n) { asm volatile("bar.sync %0, %1;" ::"r"(id), "r"(n) : "memory"); }
__device__ __forceinline__ void bar_arrive(int id, int n) { asm volatile("bar.arrive %0, %1;" ::"r"(id), "r"(n) : "memory"); }
__device__ __forceinline__ void red_relaxed(unsigned* p) { asm volatile("red.relaxed.gpu.global.add.u32 [%0], 1;" ::"l"(p) : "memory"); }
__device__ __forceinline__ unsigned ld_epoch1() { return *reinterpret_cast<volatile unsigned*>(&g_epoch) + 1u; }
__device__ __forceinline__ void cluster_sync_all() { asm volatile("barrier.cluster.arrive.relaxed.aligned;\nbarrier.cluster.wait.aligned;" ::: "memory"); }
__device__ __forceinline__ void wg_fence() { asm volatile("wgmma.fence.sync.aligned;" ::: "memory"); }
__device__ __forceinline__ void wg_commit() { asm volatile("wgmma.commit_group.sync.aligned;" ::: "memory"); }
template <int N> __device__ __forceinline__ void wg_wait() { asm volatile("wgmma.wait_group.sync.aligned %0;" ::"n"(N) : "memory"); }
template <int R> __device__ __forceinline__ void reg_inc() { asm volatile("setmaxnreg.inc.sync.aligned.u32 %0;" ::"n"(R)); }
template <int R> __device__ __forceinline__ void reg_dec() { asm volatile("setmaxnreg.dec.sync.aligned.u32 %0;" ::"n"(R)); }

__device__ __forceinline__ void tma3d_mc(uint32_t dst, const CUtensorMap* tm, uint32_t bar, int c0, int c1, int c2, uint16_t mask) {
  asm volatile("cp.async.bulk.tensor.3d.shared::cluster.global.mbarrier::complete_tx::bytes.multicast::cluster [%0], [%1, {%3,%4,%5}], [%2], %6;"
               ::"r"(dst), "l"(tm), "r"(bar), "r"(c0), "r"(c1), "r"(c2), "h"(mask) : "memory");
}
__device__ __forceinline__ void tma3d(uint32_t dst, const CUtensorMap* tm, uint32_t bar, int c0, int c1, int c2) {
  asm volatile("cp.async.bulk.tensor.3d.shared::cluster.global.mbarrier::complete_tx::bytes [%0], [%1, {%3,%4,%5}], [%2];"
               ::"r"(dst), "l"(tm), "r"(bar), "r"(c0), "r"(c1), "r"(c2) : "memory");
}
__device__ __forceinline__ void tma2d(uint32_t dst, const CUtensorMap* tm, uint32_t bar, int c0, int c1) {
  asm volatile("cp.async.bulk.tensor.2d.shared::cluster.global.mbarrier::complete_tx::bytes [%0], [%1, {%3,%4}], [%2];"
               ::"r"(dst), "l"(tm), "r"(bar), "r"(c0), "r"(c1) : "memory");
}
__device__ __forceinline__ void bulk_g2s(uint32_t dst, const void* src, uint32_t bytes, uint32_t bar) {
  asm volatile("cp.async.bulk.shared::cluster.global.mbarrier::complete_tx::bytes [%0], [%1], %2, [%3];"
               ::"r"(dst), "l"(src), "r"(bytes), "r"(bar) : "memory");
}
__device__ __forceinline__ uint64_t make_desc(uint32_t addr, uint32_t lbo, uint32_t sbo, uint32_t swz) {
  return (uint64_t)((addr & 0x3FFFF) >> 4) | ((uint64_t)(lbo >> 4) << 16) | ((uint64_t)(sbo >> 4) << 32) | ((uint64_t)swz << 62);
}
__device__ __forceinline__ float bf_round(float x) { return __bfloat162float(__float2bfloat16_rn(x)); }
__device__ __forceinline__ uint32_t pack_bf2(float lo, float hi) {
  uint32_t r; asm("cvt.rn.bf16x2.f32 %0, %1, %2;" : "=r"(r) : "f"(hi), "f"(lo)); return r;
}
__device__ __forceinline__ float bf_lo(uint32_t v) { return __uint_as_float(v << 16); }
__device__ __forceinline__ float bf_hi(uint32_t v) { return __uint_as_float(v & 0xFFFF0000u); }
__device__ __forceinline__ uint32_t lds32(uint32_t a) { uint32_t v; asm volatile("ld.volatile.shared.u32 %0, [%1];" : "=r"(v) : "r"(a) : "memory"); return v; }

template <int OFF, int SZ> __device__ __forceinline__ void wgmma_ss_n128(float (&d)[SZ], uint64_t da, uint64_t db, int scaleD) {
  asm volatile("{\n.reg .pred p;\nsetp.ne.b32 p, %66, 0;\n"
    "wgmma.mma_async.sync.aligned.m64n128k16.f32.bf16.bf16 {%0,%1,%2,%3,%4,%5,%6,%7,%8,%9,%10,%11,%12,%13,%14,%15,%16,%17,%18,%19,%20,%21,%22,%23,%24,%25,%26,%27,%28,%29,%30,%31,%32,%33,%34,%35,%36,%37,%38,%39,%40,%41,%42,%43,%44,%45,%46,%47,%48,%49,%50,%51,%52,%53,%54,%55,%56,%57,%58,%59,%60,%61,%62,%63}, %64, %65, p, 1, 1, 0, 1;\n}\n"
    : "+f"(d[OFF+0]),"+f"(d[OFF+1]),"+f"(d[OFF+2]),"+f"(d[OFF+3]),"+f"(d[OFF+4]),"+f"(d[OFF+5]),"+f"(d[OFF+6]),"+f"(d[OFF+7]),"+f"(d[OFF+8]),"+f"(d[OFF+9]),"+f"(d[OFF+10]),"+f"(d[OFF+11]),"+f"(d[OFF+12]),"+f"(d[OFF+13]),"+f"(d[OFF+14]),"+f"(d[OFF+15]),"+f"(d[OFF+16]),"+f"(d[OFF+17]),"+f"(d[OFF+18]),"+f"(d[OFF+19]),"+f"(d[OFF+20]),"+f"(d[OFF+21]),"+f"(d[OFF+22]),"+f"(d[OFF+23]),"+f"(d[OFF+24]),"+f"(d[OFF+25]),"+f"(d[OFF+26]),"+f"(d[OFF+27]),"+f"(d[OFF+28]),"+f"(d[OFF+29]),"+f"(d[OFF+30]),"+f"(d[OFF+31]),"+f"(d[OFF+32]),"+f"(d[OFF+33]),"+f"(d[OFF+34]),"+f"(d[OFF+35]),"+f"(d[OFF+36]),"+f"(d[OFF+37]),"+f"(d[OFF+38]),"+f"(d[OFF+39]),"+f"(d[OFF+40]),"+f"(d[OFF+41]),"+f"(d[OFF+42]),"+f"(d[OFF+43]),"+f"(d[OFF+44]),"+f"(d[OFF+45]),"+f"(d[OFF+46]),"+f"(d[OFF+47]),"+f"(d[OFF+48]),"+f"(d[OFF+49]),"+f"(d[OFF+50]),"+f"(d[OFF+51]),"+f"(d[OFF+52]),"+f"(d[OFF+53]),"+f"(d[OFF+54]),"+f"(d[OFF+55]),"+f"(d[OFF+56]),"+f"(d[OFF+57]),"+f"(d[OFF+58]),"+f"(d[OFF+59]),"+f"(d[OFF+60]),"+f"(d[OFF+61]),"+f"(d[OFF+62]),"+f"(d[OFF+63])
    : "l"(da), "l"(db), "r"(scaleD));
}
__device__ __forceinline__ void wgmma_rs_n64(float (&d)[32], const uint32_t (&a)[4], uint64_t db, int scaleD) {
  asm volatile("{\n.reg .pred p;\nsetp.ne.b32 p, %37, 0;\n"
    "wgmma.mma_async.sync.aligned.m64n64k16.f32.bf16.bf16 {%0,%1,%2,%3,%4,%5,%6,%7,%8,%9,%10,%11,%12,%13,%14,%15,%16,%17,%18,%19,%20,%21,%22,%23,%24,%25,%26,%27,%28,%29,%30,%31}, {%32,%33,%34,%35}, %36, p, 1, 1, 0;\n}\n"
    : "+f"(d[0]),"+f"(d[1]),"+f"(d[2]),"+f"(d[3]),"+f"(d[4]),"+f"(d[5]),"+f"(d[6]),"+f"(d[7]),"+f"(d[8]),"+f"(d[9]),"+f"(d[10]),"+f"(d[11]),"+f"(d[12]),"+f"(d[13]),"+f"(d[14]),"+f"(d[15]),"+f"(d[16]),"+f"(d[17]),"+f"(d[18]),"+f"(d[19]),"+f"(d[20]),"+f"(d[21]),"+f"(d[22]),"+f"(d[23]),"+f"(d[24]),"+f"(d[25]),"+f"(d[26]),"+f"(d[27]),"+f"(d[28]),"+f"(d[29]),"+f"(d[30]),"+f"(d[31])
    : "r"(a[0]), "r"(a[1]), "r"(a[2]), "r"(a[3]), "l"(db), "r"(scaleD));
}
__device__ __forceinline__ void wgmma_rsT_n128(float (&d)[64], const uint32_t (&a)[4], uint64_t db, int scaleD) {
  asm volatile("{\n.reg .pred p;\nsetp.ne.b32 p, %69, 0;\n"
    "wgmma.mma_async.sync.aligned.m64n128k16.f32.bf16.bf16 {%0,%1,%2,%3,%4,%5,%6,%7,%8,%9,%10,%11,%12,%13,%14,%15,%16,%17,%18,%19,%20,%21,%22,%23,%24,%25,%26,%27,%28,%29,%30,%31,%32,%33,%34,%35,%36,%37,%38,%39,%40,%41,%42,%43,%44,%45,%46,%47,%48,%49,%50,%51,%52,%53,%54,%55,%56,%57,%58,%59,%60,%61,%62,%63}, {%64,%65,%66,%67}, %68, p, 1, 1, 1;\n}\n"
    : "+f"(d[0]),"+f"(d[1]),"+f"(d[2]),"+f"(d[3]),"+f"(d[4]),"+f"(d[5]),"+f"(d[6]),"+f"(d[7]),"+f"(d[8]),"+f"(d[9]),"+f"(d[10]),"+f"(d[11]),"+f"(d[12]),"+f"(d[13]),"+f"(d[14]),"+f"(d[15]),"+f"(d[16]),"+f"(d[17]),"+f"(d[18]),"+f"(d[19]),"+f"(d[20]),"+f"(d[21]),"+f"(d[22]),"+f"(d[23]),"+f"(d[24]),"+f"(d[25]),"+f"(d[26]),"+f"(d[27]),"+f"(d[28]),"+f"(d[29]),"+f"(d[30]),"+f"(d[31]),"+f"(d[32]),"+f"(d[33]),"+f"(d[34]),"+f"(d[35]),"+f"(d[36]),"+f"(d[37]),"+f"(d[38]),"+f"(d[39]),"+f"(d[40]),"+f"(d[41]),"+f"(d[42]),"+f"(d[43]),"+f"(d[44]),"+f"(d[45]),"+f"(d[46]),"+f"(d[47]),"+f"(d[48]),"+f"(d[49]),"+f"(d[50]),"+f"(d[51]),"+f"(d[52]),"+f"(d[53]),"+f"(d[54]),"+f"(d[55]),"+f"(d[56]),"+f"(d[57]),"+f"(d[58]),"+f"(d[59]),"+f"(d[60]),"+f"(d[61]),"+f"(d[62]),"+f"(d[63])
    : "r"(a[0]), "r"(a[1]), "r"(a[2]), "r"(a[3]), "l"(db), "r"(scaleD));
}

__device__ __forceinline__ float gelu_mul(float g, float u) {
  float g2 = g * g;
  float t = g * fmaf(g2, 0.0356774081f, 0.7978845608f);
  float th; asm("tanh.approx.f32 %0, %1;" : "=f"(th) : "f"(t));
  float hg = 0.5f * g;
  return fmaf(hg, th, hg) * u;
}

__device__ __forceinline__ float2 cexpm(float al, float at, float m) {
  float mag; asm("ex2.approx.f32 %0, %1;" : "=f"(mag) : "f"(al * m));
  const float ph = at * m;
  const float k = (fabsf(ph) < 4194304.f) ? __fadd_rn(__fadd_rn(ph, 12582912.f), -12582912.f) : ph;
  const float r = (ph - k) * 6.283185307179586f;
  return make_float2(mag * __cosf(r), mag * __sinf(r));
}
__device__ __forceinline__ float2 cmul(float2 a, float2 b) { return make_float2(fmaf(a.x, b.x, -a.y * b.y), fmaf(a.x, b.y, a.y * b.x)); }
__device__ __forceinline__ float2 csq(float2 a) { return make_float2(fmaf(a.x, a.x, -a.y * a.y), 2.f * a.x * a.y); }
__device__ __forceinline__ uint32_t tf32r(float x) { return __float_as_uint(x) + 0x1000u; }
__device__ __forceinline__ void bfrag_tf32(uint32_t (&b)[2], float2 cf, float2 e) {
  b[0] = tf32r(fmaf(cf.x, e.x, -cf.y * e.y)); b[1] = tf32r(fmaf(-cf.x, e.y, -cf.y * e.x));
}
__device__ __forceinline__ void mma_tf32(float (&c)[4], const uint32_t (&a)[4], const uint32_t (&b)[2]) {
  asm volatile("mma.sync.aligned.m16n8k8.row.col.f32.tf32.tf32.f32 {%0,%1,%2,%3}, {%4,%5,%6,%7}, {%8,%9}, {%0,%1,%2,%3};"
               : "+f"(c[0]), "+f"(c[1]), "+f"(c[2]), "+f"(c[3]) : "r"(a[0]), "r"(a[1]), "r"(a[2]), "r"(a[3]), "r"(b[0]), "r"(b[1]));
}
__device__ __forceinline__ void afrag_tf32(uint32_t (&a)[4], float2 xa, float2 xb) {
  a[0] = tf32r(xa.x); a[1] = tf32r(xb.x); a[2] = tf32r(xa.y); a[3] = tf32r(xb.y);
}

struct Params {
  const __nv_bfloat16 *x, *logA, *Aim, *Cre, *Cim, *logdt, *Dskip, *wg, *wu, *wd;
  __nv_bfloat16* out;
};

__device__ __forceinline__ void ldsm4(uint32_t (&a)[4], uint32_t addr) {
  asm volatile("ldmatrix.sync.aligned.m8n8.x4.shared.b16 {%0,%1,%2,%3}, [%4];" : "=r"(a[0]), "=r"(a[1]), "=r"(a[2]), "=r"(a[3]) : "r"(addr) : "memory");
}
__device__ __forceinline__ void w_release(uint32_t bars, uint32_t st, int lane) {
  if (lane == 0) { mbar_arrive_remote(bars + 8 * (B_WEMPTY + st), 0); mbar_arrive_remote(bars + 8 * (B_WEMPTY + st), 1); }
}
__device__ __forceinline__ void gemm1_pass(float (&ag)[64], float (&au)[64], uint32_t sb, int pass, int wg, int wq, int lane, uint32_t& st, uint32_t& ph) {
  const uint32_t bars = sb + SM_BAR;
  const int arow = wg * 64 + wq * 16 + ((lane >> 3) & 1) * 8 + (lane & 7);
  const uint32_t abase = sb + SM_XN + arow * 128;
  const uint32_t asw = (uint32_t)(lane & 7), ahi = (uint32_t)(lane >> 4);
  const uint64_t uoff = pass ? (6144 >> 4) : (8192 >> 4);
  uint32_t af[2][2][4];
  uint32_t prev = 0;
  mbar_wait(bars + 8 * B_XFULL, 0);
  ldsm4(af[0][0], abase + ((ahi ^ asw) << 4));
  ldsm4(af[0][1], abase + (((2 + ahi) ^ asw) << 4));
#pragma unroll 1
  for (int k2 = 0; k2 < 8; k2++) {
#pragma unroll
    for (int hb = 0; hb < 2; hb++) {
      mbar_wait(bars + 8 * (B_WFULL + st), ph);
      wg_fence();
#pragma unroll
      for (int ks = 0; ks < 2; ks++) {
        uint64_t db = make_desc(sb + SM_W + st * W_STAGE_BYTES + ks * 1024, 2048, 512, 2);
        wgmma_rsT_n128(ag, af[hb][ks], db, (k2 | hb | ks) != 0);
        wgmma_rsT_n128(au, af[hb][ks], db + uoff, (k2 | hb | ks) != 0);
      }
      wg_commit();
      if (k2 | hb) {
        wg_wait<1>();
        w_release(bars, prev, lane);
      }
      if (hb == 0) {
        ldsm4(af[1][0], abase + k2 * 16384 + (((4 + ahi) ^ asw) << 4));
        ldsm4(af[1][1], abase + k2 * 16384 + (((6 + ahi) ^ asw) << 4));
        if (pass && (k2 & 1)) { __syncwarp(); if (lane == 0) mbar_arrive(bars + 8 * (B_GEMPTY + (k2 >> 1))); }
      } else if (k2 < 7) {
        mbar_wait(bars + 8 * (B_XFULL + k2 + 1), 0);
        ldsm4(af[0][0], abase + (k2 + 1) * 16384 + ((ahi ^ asw) << 4));
        ldsm4(af[0][1], abase + (k2 + 1) * 16384 + (((2 + ahi) ^ asw) << 4));
      }
      prev = st;
      if (++st == W_STAGES) { st = 0; ph ^= 1; }
    }
  }
  wg_wait<0>();
  w_release(bars, prev, lane);
}
__device__ __forceinline__ void gemm1_epilogue(float (&ag)[64], float (&au)[64], const uint8_t* sp, int pass, int mi, int f, int wg, int wq, int lane) {
  const int g = lane >> 2, cc = lane & 3;
  const int row = wg * 64 + wq * 16 + g;
  const float2 s0 = *reinterpret_cast<const float2*>(sp + SM_STAT + row * 8);
  const float2 s1 = *reinterpret_cast<const float2*>(sp + SM_STAT + (row + 8) * 8);
  const float nm0 = -s0.x * s0.y, nm1 = -s1.x * s1.y;
  const float2* sg = reinterpret_cast<const float2*>(sp + SM_S) + pass * 64 + cc;
  uint32_t* hp = reinterpret_cast<uint32_t*>(g_h) + ((size_t)(mi * 224 + f * 28 + pass * 16) * 128 + row) * 4 + cc;
#pragma unroll
  for (int nb = 0; nb < 16; nb++) {
    if (nb == 12 && pass) break;
    const float2 cg = sg[4 * nb], cu = sg[112 + 4 * nb];
    uint32_t v0 = pack_bf2(gelu_mul(fmaf(ag[4 * nb + 0], s0.y, nm0 * cg.x), fmaf(au[4 * nb + 0], s0.y, nm0 * cu.x)),
                           gelu_mul(fmaf(ag[4 * nb + 1], s0.y, nm0 * cg.y), fmaf(au[4 * nb + 1], s0.y, nm0 * cu.y)));
    uint32_t v1 = pack_bf2(gelu_mul(fmaf(ag[4 * nb + 2], s1.y, nm1 * cg.x), fmaf(au[4 * nb + 2], s1.y, nm1 * cu.x)),
                           gelu_mul(fmaf(ag[4 * nb + 3], s1.y, nm1 * cg.y), fmaf(au[4 * nb + 3], s1.y, nm1 * cu.y)));
    hp[nb * 512] = v0;
    hp[nb * 512 + 32] = v1;
  }
}

__device__ __forceinline__ int kidx(int l) {
  uint32_t bits = __float_as_uint((float)l);
  bits = (bits + 0x7FFFu + ((bits >> 16) & 1u)) >> 16;
  const int idx = l < 256 ? l : (int)bits - 0x4380 + 256;
  return (unsigned)l < (unsigned)kL ? idx : 641;
}
__device__ __forceinline__ void expand_table(const unsigned short* kd, uint32_t* tbl, int t128) {
  asm volatile("" : "+r"(t128));
  uint32_t w[9], nx[9];
#pragma unroll
  for (int k = 0; k < 9; k++) {
    const int l = 2 * (k * 128 + t128) - 15;
    w[k] = (uint32_t)kd[kidx(l)] | ((uint32_t)kd[kidx(l + 1)] << 16);
    nx[k] = kd[kidx(l + 2)];
  }
#pragma unroll
  for (int k = 0; k < 9; k++) {
    const int i = k * 128 + t128;
    if (k < 8 || i < 1040) {
      tbl[i] = w[k];
      tbl[i + TBL_COPY / 4] = (w[k] >> 16) | (nx[k] << 16);
    }
  }
}
__device__ __forceinline__ void conv_load(uint32_t (&a)[4][4], uint32_t ta, int Pb) {
#pragma unroll
  for (int i = 0; i < 4; i++) {
    const uint32_t p = ta + Pb * 512 + i * 64;
    a[i][0] = lds32(p); a[i][1] = lds32(p + 256); a[i][2] = lds32(p + 16); a[i][3] = lds32(p + 272);
  }
}
__device__ __forceinline__ void conv_main(float (&acc)[2][32], uint32_t ta, uint32_t ub) {
  uint32_t a[2][4][4];
  conv_load(a[0], ta, 0);
  conv_load(a[1], ta, 1);
  const uint64_t db0 = make_desc(ub + U_PAD * 128, 16, 1024, 1);
#pragma unroll
  for (int Pb = 0; Pb < 8; Pb++) {
    wg_fence();
#pragma unroll
    for (int i = 0; i < 4; i++) {
#pragma unroll
      for (int G = 1; G >= Pb / 4; G--) wgmma_rs_n64(acc[G], a[Pb & 1][i], db0 + (uint64_t)(int64_t)(8 * (64 * G - 2 * i - 16 * Pb)), (Pb | i) != 0);
    }
    wg_commit();
    if (Pb >= 1 && Pb + 1 < 8) {
      wg_wait<1>();
      conv_load(a[(Pb + 1) & 1], ta, Pb + 1);
    }
  }
  wg_wait<0>();
}

__device__ __forceinline__ void kgen_unit(const uint32_t (&pv)[4], float dt, float4* kc, int lane, float (&ka)[5][4], float& k2048) {
  const int g = lane >> 2, cc = lane & 3;
  const float fg = (float)g, fg16 = (float)(16 * g);
  const float f3 = (float)(512 + 256 * (g >> 2) + 4 * (g & 3)), f4 = (float)(1024 + 256 * (g >> 1) + 8 * (g & 1));
  {
    const float ar = -bf_round(expf(bf_lo(pv[0]))) * dt * 1.4426950408889634f;
    const float ai = bf_lo(pv[1]) * dt * 0.15915494309189535f;
    const float2 c = make_float2(2.f * (bf_lo(pv[2]) * dt), 2.f * (bf_lo(pv[3]) * dt));
    const float2 e8 = cexpm(ar, ai, 8.f), e128 = cexpm(ar, ai, 128.f);
    const float2 k1 = cmul(c, cexpm(ar, ai, 256.f));
    const float2 e2048 = cexpm(ar, ai, 2048.f);
    k2048 += fmaf(c.x, e2048.x, -c.y * e2048.y);
    __syncwarp();
    kc[lane * 3 + 0] = make_float4(ar, ai, e8.x, e8.y);
    kc[lane * 3 + 1] = make_float4(e128.x, e128.y, c.x, c.y);
    kc[lane * 3 + 2] = make_float4(k1.x, k1.y, 0.f, 0.f);
    __syncwarp();
  }
  float4 n0 = kc[cc * 3 + 0], n1 = kc[cc * 3 + 1], n2 = kc[cc * 3 + 2];
#pragma unroll 2
  for (int s = 0; s < 8; s++) {
    const float4 q0 = n0, q1 = n1, q2 = n2;
    const int sn = ((s + 1) & 7) * 4 + cc;
    n0 = kc[sn * 3 + 0]; n1 = kc[sn * 3 + 1]; n2 = kc[sn * 3 + 2];
    const float2 Y = cexpm(q0.x, q0.y, fg), X = cexpm(q0.x, q0.y, fg16);
    const float2 Z3 = cexpm(q0.x, q0.y, f3), Z4 = cexpm(q0.x, q0.y, f4);
    const float2 Xb = cmul(X, make_float2(q1.x, q1.y));
    const float2 Yb = cmul(Y, make_float2(q0.z, q0.w));
    const float2 cA = make_float2(q1.z, q1.w);
    uint32_t a1[4], b0[2], b1[2], b2[2], b3[2], b4[2];
    afrag_tf32(a1, X, Xb);
    bfrag_tf32(b0, cA, Y); bfrag_tf32(b1, cA, Yb); bfrag_tf32(b2, make_float2(q2.x, q2.y), csq(Y));
    bfrag_tf32(b3, cA, Z3); bfrag_tf32(b4, cA, Z4);
    mma_tf32(ka[0], a1, b0); mma_tf32(ka[1], a1, b1); mma_tf32(ka[2], a1, b2); mma_tf32(ka[3], a1, b3); mma_tf32(ka[4], a1, b4);
  }
}
__device__ __forceinline__ void load_prm(uint32_t (&pv)[4], const Params& P, int n) {
  pv[0] = __ldg(reinterpret_cast<const unsigned short*>(P.logA) + n);
  pv[1] = __ldg(reinterpret_cast<const unsigned short*>(P.Aim) + n);
  pv[2] = __ldg(reinterpret_cast<const unsigned short*>(P.Cre) + n);
  pv[3] = __ldg(reinterpret_cast<const unsigned short*>(P.Cim) + n);
}

__device__ __forceinline__ void conv_channel(uint8_t* sp, uint32_t sb, int ch, int tbl_off, int red_off, int barid, float dsk, int t128, bool wait_u) {
  asm volatile("" : "+r"(t128), "+r"(sb));
  const int wq = t128 >> 5, lane = t128 & 31, g = lane >> 2, cc = lane & 3;
  const uint32_t toff = (g & 1) * TBL_COPY + (4 * wq + (g >> 1) + cc) * 4;
  float acc[2][32];
  bar_sync(barid, 128);
  if (wait_u) mbar_wait(sb + SM_BAR + 8 * B_UFULL, 0);
  {
    conv_main(acc, sb + tbl_off + toff, sb + SM_CV_U + ch * 32);
  }
  float E[16][2];
#pragma unroll
  for (int nb = 0; nb < 16; nb++) {
#pragma unroll
    for (int e = 0; e < 2; e++)
      E[nb][e] = acc[nb >> 3][4 * (nb & 7) + e] + (nb > 0 ? acc[(nb - 1) >> 3][4 * ((nb - 1) & 7) + 2 + e] : 0.f);
  }
  {
    float* xb = reinterpret_cast<float*>(sp + red_off) + (wq >> 1) * 2048 + 8 * (wq & 1) + g;
#pragma unroll
    for (int nb = 0; nb < 16; nb++) {
      float* u = xb + (4 * nb + cc) * 32;
      const int r = 8 * (wq & 1) + g;
      u[((r) ^ (8 * cc)) - r] = E[nb][0];
      u[((16 + r) ^ (8 * cc)) - r] = E[nb][1];
    }
  }
  bar_sync(barid, 128);
  {
    const float* rb = reinterpret_cast<const float*>(sp + red_off);
    const int i = t128, ip = i - 1;
    const uint4 u1 = *reinterpret_cast<const uint4*>(sp + SM_CV_U + (U_PAD + i) * 128 + (((2 * ch + 1) ^ (i & 7)) << 4));
    const uint4 u0 = *reinterpret_cast<const uint4*>(sp + SM_CV_U + (U_PAD + i) * 128 + (((2 * ch) ^ (i & 7)) << 4));
    const uint32_t uw[8] = {u1.w, u1.z, u1.y, u1.x, u0.w, u0.z, u0.y, u0.x};
    uint32_t o[8];
#pragma unroll
    for (int q = 0; q < 4; q++) {
      float4 v = *reinterpret_cast<const float4*>(rb + (i >> 1) * 32 + ((((i & 1) << 4) + 4 * q) ^ (8 * ((i >> 1) & 3))));
      if (i > 0) {
        const float4 h = *reinterpret_cast<const float4*>(rb + 2048 + (ip >> 1) * 32 + ((((ip & 1) << 4) + 4 * q) ^ (8 * ((ip >> 1) & 3))));
        v.x += h.x; v.y += h.y; v.z += h.z; v.w += h.w;
      }
      const uint32_t c0 = pack_bf2(v.x, v.y), c1 = pack_bf2(v.z, v.w);
      const uint32_t s0 = pack_bf2(bf_hi(uw[2 * q]) * dsk, bf_lo(uw[2 * q]) * dsk), s1 = pack_bf2(bf_hi(uw[2 * q + 1]) * dsk, bf_lo(uw[2 * q + 1]) * dsk);
      o[2 * q] = pack_bf2(bf_lo(c0) + bf_lo(s0), bf_hi(c0) + bf_hi(s0));
      o[2 * q + 1] = pack_bf2(bf_lo(c1) + bf_lo(s1), bf_hi(c1) + bf_hi(s1));
    }
    uint4* ys = reinterpret_cast<uint4*>(sp + tbl_off + i * 32);
    ys[0] = make_uint4(o[0], o[1], o[2], o[3]);
    ys[1] = make_uint4(o[4], o[5], o[6], o[7]);
  }
}

struct Fr16 { uint32_t v[16]; };
__device__ __forceinline__ void final_out(const __nv_bfloat16* px, __nv_bfloat16* pout, int t0, int col0, int cc, int lane, unsigned ytarget, Fr16 frs) {
  const uint32_t (&fr)[16] = frs.v;
  uint32_t xr[16], yr[16];
  {
    const uint32_t* xp = reinterpret_cast<const uint32_t*>(px + (size_t)t0 * kD + col0) + cc;
#pragma unroll
    for (int i = 0; i < 8; i++) { xr[2 * i] = __ldg(xp + 4 * i); xr[2 * i + 1] = __ldg(xp + 4 * i + 8 * (kD / 2)); }
  }
  if (lane == 0) flag_wait(&g_y_cnt[col0 >> 6], ytarget);
  __syncwarp();
  const uint32_t* yp = reinterpret_cast<const uint32_t*>(g_y) + ((size_t)((col0 >> 2) + (cc >> 1)) * kL + t0) * 2 + (cc & 1);
#pragma unroll
  for (int i = 0; i < 8; i++) { yr[2 * i] = __ldcg(yp + (size_t)i * 4 * kL); yr[2 * i + 1] = __ldcg(yp + (size_t)i * 4 * kL + 16); }
  uint32_t* op = reinterpret_cast<uint32_t*>(pout + (size_t)t0 * kD + col0) + cc;
#pragma unroll
  for (int i = 0; i < 16; i++) {
    op[4 * (i >> 1) + (i & 1) * 8 * (kD / 2)] =
        pack_bf2(bf_round(bf_lo(xr[i]) + bf_lo(yr[i])) + bf_lo(fr[i]), bf_round(bf_hi(xr[i]) + bf_hi(yr[i])) + bf_hi(fr[i]));
  }
}

__global__ void __cluster_dims__(2, 1, 1) __launch_bounds__(512, 1)
fused_kernel(const __grid_constant__ CUtensorMap tmG4, const __grid_constant__ CUtensorMap tmU4,
             const __grid_constant__ CUtensorMap tmG3, const __grid_constant__ CUtensorMap tmU3,
             const __grid_constant__ CUtensorMap tmWd, const __grid_constant__ CUtensorMap tmU,
             const __grid_constant__ CUtensorMap tmX, const Params P) {
  extern __shared__ uint8_t smem_raw[];
  const uint32_t sb = (s2u(smem_raw) + 1023u) & ~1023u;
  uint8_t* sp = smem_raw + (sb - s2u(smem_raw));
  const uint32_t bars = sb + SM_BAR;
  const int tid = threadIdx.x, warp = tid >> 5, lane = tid & 31;
  const uint32_t rank = blockIdx.x & 1;
  const int pair = blockIdx.x >> 1;
  const int f = pair & 7, mi = 2 * (pair >> 3) + (int)rank;
  const int mi2 = pair >> 2, nj = pair & 3;

  if (tid == 0) TS(0);
  if (sb - s2u(smem_raw) + SM_TOTAL > SMEM_BYTES) __trap();
  uint32_t pv[4], ldtb;
  load_prm(pv, P, (blockIdx.x * 4 + (warp & 3)) * kN + (warp >> 2) * 32 + lane);
  ldtb = __ldg(reinterpret_cast<const unsigned short*>(P.logdt) + blockIdx.x * 4 + (warp & 3));
  if (tid == 384) {
    for (int i = 0; i < W_STAGES; i++) { mbar_init(bars + 8 * (B_WFULL + i), 1); mbar_init(bars + 8 * (B_WEMPTY + i), 16); }
    for (int i = 0; i < G2_STAGES; i++) { mbar_init(bars + 8 * (B_GFULL + i), 2); mbar_init(bars + 8 * (B_GEMPTY + i), 8); }
    for (int i = 0; i < 8; i++) mbar_init(bars + 8 * (B_XFULL + i), 1);
    mbar_init(bars + 8 * B_P1DONE, 8);
    mbar_init(bars + 8 * B_UFULL, 1); mbar_init(bars + 8 * (B_UFULL + 1), 1);
    mbar_init(bars + 8 * B_PEERRDY, 4);
    mbar_init(bars + 8 * B_REDFULL, 1);
    mbar_init(bars + 8 * B_EPIRDY, 128);
    mbar_init(bars + 8 * B_KGDONE, 128);
    mbar_init(bars + 8 * B_SCRFREE, 128);
    asm volatile("fence.mbarrier_init.release.cluster;" ::: "memory");
    fence_proxy_smem();
    mbar_expect(bars + 8 * B_XFULL, 16384);
    tma2d(sb + SM_XN, &tmX, bars + 8 * B_XFULL, 0, mi * 128);
  }
  cluster_sync_all();
  if (tid == 0) TS(1);

  const int wgid = warp >> 2, wq = warp & 3, t128 = tid & 127;
  const int g = lane >> 2, cc = lane & 3;
  if (tid == 384) {
    for (int it = 0; it < W_STAGES; it++) {
      mbar_expect(bars + 8 * (B_WFULL + it), 16384);
      tma3d_mc(sb + SM_W + it * W_STAGE_BYTES + rank * 8192, rank ? &tmU4 : &tmG4, bars + 8 * (B_WFULL + it), 0, it * 32, f * 7, 3);
    }
  } else if (tid == 416) {
    for (int kx = 1; kx < 3; kx++) {
      mbar_expect(bars + 8 * (B_XFULL + kx), 16384);
      tma2d(sb + SM_XN + kx * 16384, &tmX, bars + 8 * (B_XFULL + kx), kx * 64, mi * 128);
    }
    mbar_expect(bars + 8 * B_REDFULL, 32768);
  }
  __syncwarp();
  if (wgid == 2) {
    reg_dec<104>();
    {
      const uint4* xp = reinterpret_cast<const uint4*>(P.x + (size_t)(blockIdx.x * 16 + wq * 4 + (lane >> 3)) * kD) + (lane & 7);
      uint4 xv[8];
#pragma unroll
      for (int j = 0; j < 8; j++) xv[j] = __ldg(xp + j * 8);
      float s = 0.f;
#pragma unroll
      for (int j = 0; j < 8; j++)
        s += (bf_lo(xv[j].x) + bf_hi(xv[j].x)) + (bf_lo(xv[j].y) + bf_hi(xv[j].y)) + (bf_lo(xv[j].z) + bf_hi(xv[j].z)) + (bf_lo(xv[j].w) + bf_hi(xv[j].w));
#pragma unroll
      for (int o = 4; o > 0; o >>= 1) s += __shfl_xor_sync(0xffffffffu, s, o);
      const float mean = s * (1.f / 512.f);
      float q = 0.f;
#pragma unroll
      for (int j = 0; j < 8; j++) {
        const uint32_t u[4] = {xv[j].x, xv[j].y, xv[j].z, xv[j].w};
#pragma unroll
        for (int i = 0; i < 4; i++) { float d0 = bf_lo(u[i]) - mean, d1 = bf_hi(u[i]) - mean; q = fmaf(d0, d0, q); q = fmaf(d1, d1, q); }
      }
#pragma unroll
      for (int o = 4; o > 0; o >>= 1) q += __shfl_xor_sync(0xffffffffu, q, o);
      const float vb = bf_round(q * (1.f / 512.f));
      const float den = bf_round(sqrtf(bf_round(vb + 1e-5f)));
      if ((lane & 7) == 0) {
        const float2 st2 = make_float2(bf_round(mean), 1.f / den);
        const int r = wq * 4 + (lane >> 3);
        *reinterpret_cast<float2*>(sp + SM_LNS + r * 8) = st2;
        g_stat[blockIdx.x * 16 + r] = st2;
      }
    }
    {
      const int rg = lane >= 14 ? 1 : 0, c14 = lane < 28 ? lane - 14 * rg : 0;
      const uint4* wp = reinterpret_cast<const uint4*>((wq >> 1 ? P.wu : P.wg) + (size_t)(mi * 32 + rg * 16) * kF + f * 224 + (wq & 1) * 112) + c14;
      uint4 wv[16];
#pragma unroll
      for (int j = 0; j < 16; j++) wv[j] = __ldg(wp + (size_t)j * (kF / 8));
      float cs[8] = {0, 0, 0, 0, 0, 0, 0, 0};
#pragma unroll
      for (int j = 0; j < 16; j++) {
        cs[0] += bf_lo(wv[j].x); cs[1] += bf_hi(wv[j].x); cs[2] += bf_lo(wv[j].y); cs[3] += bf_hi(wv[j].y);
        cs[4] += bf_lo(wv[j].z); cs[5] += bf_hi(wv[j].z); cs[6] += bf_lo(wv[j].w); cs[7] += bf_hi(wv[j].w);
      }
#pragma unroll
      for (int j = 0; j < 8; j++) cs[j] += __shfl_down_sync(0xffffffffu, cs[j], 14);
      if (lane < 14) {
        float4* sd = reinterpret_cast<float4*>(g_S + (size_t)(mi * 8 + f) * 448 + (wq >> 1) * 224 + (wq & 1) * 112) + lane * 2;
        sd[0] = make_float4(cs[0], cs[1], cs[2], cs[3]);
        sd[1] = make_float4(cs[4], cs[5], cs[6], cs[7]);
      }
    }
    bar_sync(3, 128);
    if (t128 == 96) { fence_gpu(); red_relaxed(&g_xn_cnt[blockIdx.x >> 3]); red_relaxed(&g_s_cnt[f]); }
    __syncwarp();
    if (t128 == 0) TS(28);
  }
  float ka[5][4] = {}, k2048 = 0.f;
  {
    asm volatile("" : "+r"(pv[0]), "+r"(pv[1]), "+r"(pv[2]), "+r"(pv[3]), "+r"(ldtb));
    const float ldt = bf_lo(ldtb);
    const int slot = (wgid == 3 ? 8 : wgid * 4) + wq;
    kgen_unit(pv, bf_round(expf(ldt)), reinterpret_cast<float4*>(sp + (warp < 10 ? SM_KCC + warp * 1536 : SM_KC + (warp - 10) * 1536)), lane, ka, k2048);
    if (wgid != 2) {
      float* kp = reinterpret_cast<float*>(sp + SM_KPART) + slot * (21 * 32) + lane;
#pragma unroll
      for (int i = 0; i < 20; i++) kp[i * 32] = ka[i >> 2][i & 3];
      kp[20 * 32] = k2048;
      bar_arrive(8, 512);
    }
    if (tid == 0) TS(14);
  }
  if (wgid == 3) {
    reg_dec<56>();
    bar_sync(13, 128);
    if (warp < 14) {
      const int pw = warp - 12;
      const unsigned epoch1 = ld_epoch1();
      if (lane == 0) {
        uint32_t st = pw, ph = 0;
#pragma unroll 1
        for (int it = W_STAGES + pw; it < 32; it += 2) {
          mbar_wait(bars + 8 * (B_WEMPTY + st), ph);
          const int kb = it & 15;
          if ((it & 1) == 0 && it >= 6 && it <= 14) {
            const int kx = it >> 1;
            if (kx == 5) mbar_wait(bars + 8 * B_SCRFREE, 0);
            mbar_expect(bars + 8 * (B_XFULL + kx), 16384);
            tma2d(sb + SM_XN + kx * 16384, &tmX, bars + 8 * (B_XFULL + kx), kx * 64, mi * 128);
          }
          if (it < 16) {
            mbar_expect(bars + 8 * (B_WFULL + st), 16384);
            tma3d_mc(sb + SM_W + st * W_STAGE_BYTES + rank * 8192, rank ? &tmU4 : &tmG4, bars + 8 * (B_WFULL + st), 0, kb * 32, f * 7, 3);
          } else {
            mbar_expect(bars + 8 * (B_WFULL + st), 12288);
            tma3d_mc(sb + SM_W + st * W_STAGE_BYTES + rank * 6144, rank ? &tmU3 : &tmG3, bars + 8 * (B_WFULL + st), 0, kb * 32, f * 7 + 4, 3);
          }
          st += 2;
          if (st >= W_STAGES) { st -= W_STAGES; ph ^= 1; }
        }
      }
      __syncwarp();
      reg_dec<32>();
      if (pw == 1) {
        if (lane < 4) flag_wait(&g_h_cnt[(mi2 * 8 + 4 * (int)rank + lane) * 2], epoch1 * 2u);
        __syncwarp();
        if (lane == 0) fence_proxy_async();
      }
      uint32_t st = 0, ph = 0;
      int col = 224 * 4 * (int)rank, sub = 0, fs = 4 * (int)rank;
#pragma unroll 1
      for (int it = 0; it < 14; it++) {
        if (it == 8) {
          fs = 4 * (int)rank; col = 224 * fs + 128; sub = 0;
          if (pw == 1) {
            __syncwarp();
            if (lane < 4) flag_wait(&g_h_cnt[(mi2 * 8 + 4 * (int)rank + lane) * 2 + 1], epoch1 * 2u);
            __syncwarp();
            if (lane == 0) fence_proxy_async();
          }
        }
        if (lane == 0) {
          mbar_wait(bars + 8 * (B_GEMPTY + st), ph);
          mbar_expect(bars + 8 * (B_GFULL + st), 16384);
          const uint32_t sa = sb + SM_XN + st * G2_STAGE_BYTES;
#pragma unroll 1
          for (int hb = 0; hb < 2; hb++) {
            if (pw == 0) {
              tma3d(sa + 16384 + hb * 8192, &tmWd, bars + 8 * (B_GFULL + st), 0, col, nj * 2 + (int)rank);
              tma3d(sa + 16384 + hb * 8192 + 4096, &tmWd, bars + 8 * (B_GFULL + st), 0, col, nj * 2 + (int)(rank ^ 1));
            }
            else bulk_g2s(sa + hb * 8192, reinterpret_cast<const char*>(g_h) + ((size_t)mi2 * 224 + (col >> 3)) * 2048, 8192, bars + 8 * (B_GFULL + st));
            col += 32; sub++;
            if (it < 8) { if (sub == 4) { sub = 0; fs++; col = 224 * fs; } }
            else if (sub == 3) { sub = 0; fs++; col = 224 * fs + 128; }
          }
        }
        if (++st == G2_STAGES) { st = 0; ph ^= 1; }
      }
      __syncwarp();
    } else {
      if (warp == 14) {
        reg_dec<32>();
#pragma unroll 1
        for (int e = 0; e < 4; e++) {
          bar_sync(e < 2 ? 1 + e : 12 + e, 128 + 32);
          if (lane == 0) { fence_gpu(); red_relaxed(&g_h_cnt[(mi * 8 + f) * 2 + (e >> 1)]); }
          __syncwarp();
        }
      } else {
        reg_dec<32>();
        if (lane == 0) {
          asm volatile("cp.async.bulk.prefetch.L2.global [%0], %1;" ::"l"(reinterpret_cast<const char*>(P.wd) + (size_t)blockIdx.x * 14336), "r"(14336) : "memory");
        }
        if (lane == 0) {
          flag_wait(&g_xn_all, ld_epoch1() * 128u);
          fence_proxy_async();
          mbar_wait(bars + 8 * B_P1DONE, 0);
          mbar_expect(bars + 8 * B_UFULL, U_BYTES);
          tma3d(sb + SM_CV_U, &tmU, bars + 8 * B_UFULL, 0, -U_PAD, blockIdx.x);
        }
        __syncwarp();
      }
    }
    return;
  }
  if (wgid < 2) {
    reg_inc<176>();
    uint32_t st = 0, ph = 0;
#pragma unroll 1
    for (int pass = 0; pass < 2; pass++) {
      float ag[64], au[64];
      gemm1_pass(ag, au, sb, pass, wgid, wq, lane, st, ph);
      if (tid == 0) TS(3 + 2 * pass);
      if (pass && lane == 0) mbar_arrive(bars + 8 * B_P1DONE);
      mbar_wait(bars + 8 * B_EPIRDY, 0);
      gemm1_epilogue(ag, au, sp, pass, mi, f, wgid, wq, lane);
      bar_arrive(1 + 13 * pass + wgid, 128 + 32);
      if (tid == 0) TS(4 + 2 * pass);
    }
    if (wgid == 1) {
      reg_dec<152>();
      mbar_wait(bars + 8 * B_KGDONE, 0);
      mbar_wait(bars + 8 * B_P1DONE, 0);
    } else {
    float acc0[64], acc1[64];
    uint32_t prev = 0;
    st = 0; ph = 0;
#pragma unroll 1
    for (int it = 0; it < 14; it++) {
      mbar_wait(bars + 8 * (B_GFULL + st), ph);
      if (tid == 0 && it == 0) TS(7);
      if (tid == 0 && it == 8) TS(8);
      const uint32_t sa = sb + SM_XN + st * G2_STAGE_BYTES;
#pragma unroll
      for (int ks = 0; ks < 4; ks++) {
        uint64_t da = make_desc(sa + ks * 4096, 2048, 128, 0);
        uint64_t db = make_desc(sa + 16384 + (ks >> 1) * 8192 + (ks & 1) * 2048, 4096, 1024, 1);
        wg_fence();
        wgmma_ss_n128<0>(acc0, da, db, (it | ks) != 0);
        wgmma_ss_n128<0>(acc1, da + (1024 >> 4), db, (it | ks) != 0);
        wg_commit();
        wg_wait<1>();
        if (ks == 0 && it > 0 && lane < 2) mbar_arrive(bars + 8 * (B_GEMPTY + prev));
      }
      prev = st;
      if (++st == G2_STAGES) { st = 0; ph ^= 1; }
    }
    wg_wait<0>();
    if (tid == 0) TS(9);
    if (lane == 0) mbar_arrive_remote(bars + 8 * B_PEERRDY, rank ^ 1);
    mbar_wait_cluster(bars + 8 * B_PEERRDY, 0);
    {
      uint32_t rdst, rbar;
      asm volatile("mapa.shared::cluster.u32 %0, %1, %2;" : "=r"(rdst) : "r"(sb + SM_XN + (uint32_t)tid * 16), "r"(rank ^ 1));
      asm volatile("mapa.shared::cluster.u32 %0, %1, %2;" : "=r"(rbar) : "r"(bars + 8 * B_REDFULL), "r"(rank ^ 1));
#pragma unroll
      for (int i = 0; i < 16; i++) {
        const float* a = (i < 8 ? acc0 : acc1) + 32 + 4 * (i & 7);
        asm volatile("st.async.shared::cluster.mbarrier::complete_tx::bytes.v4.f32 [%0], {%1,%2,%3,%4}, [%5];"
                     ::"r"(rdst + i * 2048), "f"(a[0]), "f"(a[1]), "f"(a[2]), "f"(a[3]), "r"(rbar) : "memory");
      }
    }
    mbar_wait_cluster(bars + 8 * B_REDFULL, 0);
    if (tid == 0) TS(11);
    {
      float4* rp = reinterpret_cast<float4*>(sp + SM_XN) + tid;
#pragma unroll
      for (int i = 0; i < 16; i++) {
        const float* a = (i < 8 ? acc0 : acc1) + 4 * (i & 7);
        const float4 o = rp[i * 128];
        *reinterpret_cast<uint2*>(rp + i * 128) = make_uint2(pack_bf2(a[0] + o.x, a[1] + o.y), pack_bf2(a[2] + o.z, a[3] + o.w));
      }
    }
    }
  } else {
    {
      bar_sync(8, 512);
#pragma unroll 1
      for (int w2 = 0; w2 < 3; w2++) {
        const float* kp = reinterpret_cast<const float*>(sp + SM_KPART) + (wq + 4 * w2) * (21 * 32) + lane;
#pragma unroll
        for (int i = 0; i < 20; i++) ka[i >> 2][i & 3] += kp[i * 32];
        k2048 += kp[20 * 32];
      }
      fence_proxy_smem();
      mbar_arrive(bars + 8 * B_SCRFREE);
#pragma unroll
      for (int o = 16; o > 0; o >>= 1) k2048 += __shfl_xor_sync(0xffffffffu, k2048, o);
      uint32_t* kd = reinterpret_cast<uint32_t*>(sp + SM_KD + wq * KD_STRIDE * 2);
      kd[(16 * g + 2 * cc) >> 1] = pack_bf2(ka[0][0], ka[0][1]);
      kd[(16 * (g + 8) + 2 * cc) >> 1] = pack_bf2(ka[0][2], ka[0][3]);
      kd[(16 * g + 8 + 2 * cc) >> 1] = pack_bf2(ka[1][0], ka[1][1]);
      kd[(16 * (g + 8) + 8 + 2 * cc) >> 1] = pack_bf2(ka[1][2], ka[1][3]);
      kd[(256 + 8 * g + 2 * cc) >> 1] = pack_bf2(ka[2][0], ka[2][1]);
      kd[(256 + 8 * (g + 8) + 2 * cc) >> 1] = pack_bf2(ka[2][2], ka[2][3]);
      kd[(384 + 64 * (cc >> 1) + 4 * g + 2 * (cc & 1)) >> 1] = pack_bf2(ka[3][0], ka[3][1]);
      kd[(384 + 64 * (cc >> 1) + 4 * (g + 8) + 2 * (cc & 1)) >> 1] = pack_bf2(ka[3][2], ka[3][3]);
      kd[(512 + 32 * cc + 2 * g) >> 1] = pack_bf2(ka[4][0], ka[4][1]);
      kd[(512 + 32 * cc + 2 * (g + 8)) >> 1] = pack_bf2(ka[4][2], ka[4][3]);
      if (lane == 0) kd[320] = pack_bf2(k2048, 0.f);
      if (t128 == 0) TS(16);
    }
    {
      const unsigned epoch1 = ld_epoch1();
      if (lane == 0) flag_wait(&g_xn_cnt[mi], epoch1 * 8u);
      if (lane == 1) flag_wait(&g_s_cnt[f], epoch1 * 16u);
      __syncwarp();
      if (t128 < 112) {
        const float4* sp4 = reinterpret_cast<const float4*>(g_S + f * 448) + t128;
        const float2 sv = __ldcg(g_stat + mi * 128 + t128);
        float4 v[16];
#pragma unroll
        for (int j = 0; j < 16; j++) v[j] = __ldcg(sp4 + j * (8 * 112));
        float4 a = v[0];
#pragma unroll
        for (int j = 1; j < 16; j++) { a.x += v[j].x; a.y += v[j].y; a.z += v[j].z; a.w += v[j].w; }
        reinterpret_cast<float4*>(sp + SM_S)[t128] = a;
        reinterpret_cast<float2*>(sp + SM_STAT)[t128] = sv;
      } else {
        reinterpret_cast<float2*>(sp + SM_STAT)[t128] = __ldcg(g_stat + mi * 128 + t128);
      }
      mbar_arrive(bars + 8 * B_EPIRDY);
      if (t128 == 0) TS(25);
    }
#pragma unroll 1
      for (int p = t128; p < 256; p += 128) {
        const uint32_t* xp = reinterpret_cast<const uint32_t*>(P.x + (size_t)(blockIdx.x * 16) * kD) + p;
        uint32_t w[16];
#pragma unroll
        for (int r = 0; r < 16; r++) w[r] = __ldg(xp + r * (kD / 2));
#pragma unroll
        for (int r = 0; r < 16; r++) {
          const float2 st2 = *reinterpret_cast<const float2*>(sp + SM_LNS + r * 8);
          w[r] = pack_bf2(bf_round(bf_lo(w[r]) - st2.x) * st2.y, bf_round(bf_hi(w[r]) - st2.x) * st2.y);
        }
        uint32_t ck[4][4];
#pragma unroll
        for (int q = 0; q < 2; q++) {
          const int rb = 15 - 8 * q;
#pragma unroll
          for (int e = 0; e < 4; e++) {
            ck[q][e] = __byte_perm(w[rb - 2 * e], w[rb - 2 * e - 1], 0x5410);
            ck[2 + q][e] = __byte_perm(w[rb - 2 * e], w[rb - 2 * e - 1], 0x7632);
          }
        }
        const bool odd = lane & 1;
        uint4* dT = reinterpret_cast<uint4*>(g_xnT) + ((size_t)(p >> 1) * 128 + blockIdx.x) * 8 + (odd ? 1 : 0);
        uint32_t r0[4], r1[4];
#pragma unroll
        for (int e = 0; e < 4; e++) {
          r0[e] = __shfl_xor_sync(0xffffffffu, odd ? ck[0][e] : ck[1][e], 1);
          r1[e] = __shfl_xor_sync(0xffffffffu, odd ? ck[2][e] : ck[3][e], 1);
        }
        dT[0] = odd ? make_uint4(r0[0], r0[1], r0[2], r0[3]) : make_uint4(ck[0][0], ck[0][1], ck[0][2], ck[0][3]);
        dT[2] = odd ? make_uint4(r1[0], r1[1], r1[2], r1[3]) : make_uint4(ck[2][0], ck[2][1], ck[2][2], ck[2][3]);
        dT[4] = odd ? make_uint4(ck[1][0], ck[1][1], ck[1][2], ck[1][3]) : make_uint4(r0[0], r0[1], r0[2], r0[3]);
        dT[6] = odd ? make_uint4(ck[3][0], ck[3][1], ck[3][2], ck[3][3]) : make_uint4(r1[0], r1[1], r1[2], r1[3]);
      }
    bar_sync(3, 128);
    if (t128 == 96) { fence_gpu(); red_relaxed(&g_xn_all); TS(31); }
#pragma unroll 1
    for (int ch = 0; ch < 4; ch++) {
      if (ch == 3) mbar_wait(bars + 8 * B_P1DONE, 0);
      expand_table(reinterpret_cast<const unsigned short*>(sp + SM_KD + ch * KD_STRIDE * 2),
                   reinterpret_cast<uint32_t*>(sp + (ch == 0 ? SM_CV_TBL0 : (ch == 3 ? SM_CV_TBL3 : SM_CV_TBL12 + (ch - 1) * TBL_BYTES))), t128);
    }
    mbar_arrive(bars + 8 * B_KGDONE);
    reg_inc<152>();
  }
  if (wgid != 0) {
    const int chb = wgid == 2 ? 0 : 2;
    const float dsk_l = __bfloat162float(P.Dskip[blockIdx.x * 4 + chb + (lane & 1)]);
    if (tid == 256) TS(17);
#pragma unroll 1
    for (int c2 = 0; c2 < 2; c2++) {
      const int ch = chb + c2;
      conv_channel(sp, sb, ch, ch == 0 ? SM_CV_TBL0 : (ch == 3 ? SM_CV_TBL3 : SM_CV_TBL12 + (ch - 1) * TBL_BYTES), SM_CV_RED + (2 - wgid) * 16384, wgid == 2 ? 3 : 11,
                   __shfl_sync(0xffffffffu, dsk_l, c2), t128, c2 == 0);
      if (tid == 256) TS(20 + c2);
    }
    bar_sync(10, 256);
    {
      const uint2* y0 = reinterpret_cast<const uint2*>(sp + SM_CV_TBL0);
      const uint2* y1 = reinterpret_cast<const uint2*>(sp + SM_CV_TBL12);
      const uint2* y2 = reinterpret_cast<const uint2*>(sp + SM_CV_TBL12 + TBL_BYTES);
      const uint2* y3 = reinterpret_cast<const uint2*>(sp + SM_CV_TBL3);
      uint4* yp = reinterpret_cast<uint4*>(g_y) + (size_t)blockIdx.x * 1024;
#pragma unroll
      for (int it = 0; it < 2; it++) {
        const int q = it * 256 + tid - 128;
        const uint2 a = y0[q], bb = y1[q], c = y2[q], d = y3[q];
        yp[2 * q] = make_uint4(__byte_perm(a.x, bb.x, 0x5410), __byte_perm(c.x, d.x, 0x5410), __byte_perm(a.x, bb.x, 0x7632), __byte_perm(c.x, d.x, 0x7632));
        yp[2 * q + 1] = make_uint4(__byte_perm(a.y, bb.y, 0x5410), __byte_perm(c.y, d.y, 0x5410), __byte_perm(a.y, bb.y, 0x7632), __byte_perm(c.y, d.y, 0x7632));
      }
    }
    if (wgid == 1) {
      bar_arrive(12, 256);
    } else {
      bar_sync(12, 256);
      if (t128 == 0) { fence_gpu(); red_relaxed(&g_y_cnt[blockIdx.x >> 4]); TS(24); }
    }
  }
  const unsigned epoch1 = ld_epoch1();
  if (wgid < 2) {
    bar_sync(9, 256);
    Fr16 frs;
    const uint2* stash = reinterpret_cast<const uint2*>(sp + SM_XN + wgid * 16384) + t128 * 2;
#pragma unroll
    for (int i = 0; i < 8; i++) { const uint2 v = stash[i * 256]; frs.v[2 * i] = v.x; frs.v[2 * i + 1] = v.y; }
    final_out(P.x, P.out, mi2 * 128 + wgid * 64 + wq * 16 + g, nj * 128 + (int)rank * 64, cc, lane, epoch1 * 16u, frs);
    if (tid == 0) TS(12);
  }
  if (wgid != 0) { bar_arrive(4, 384); return; }
  bar_sync(4, 384);
  if (tid == 0) {
    TS(13);
    unsigned old = atomicAdd(&g_done, 1u);
    if (old == gridDim.x - 1) { g_done = 0; __threadfence(); g_epoch = epoch1; }
  }
}

typedef CUresult (*EncFn)(CUtensorMap*, CUtensorMapDataType, cuuint32_t, void*, const cuuint64_t*, const cuuint64_t*,
                          const cuuint32_t*, const cuuint32_t*, CUtensorMapInterleave, CUtensorMapSwizzle,
                          CUtensorMapL2promotion, CUtensorMapFloatOOBfill);

void make_map(EncFn enc, CUtensorMap* tm, const void* base, int W, int rows, int cols, int boxRows, int boxGroups, CUtensorMapSwizzle sw) {
  cuuint64_t dims[3] = {(cuuint64_t)W, (cuuint64_t)rows, (cuuint64_t)(cols / W)};
  cuuint64_t str[2] = {(cuuint64_t)cols * 2, (cuuint64_t)W * 2};
  cuuint32_t box[3] = {(cuuint32_t)W, (cuuint32_t)boxRows, (cuuint32_t)boxGroups};
  cuuint32_t es[3] = {1, 1, 1};
  enc(tm, CU_TENSOR_MAP_DATA_TYPE_BFLOAT16, 3, const_cast<void*>(base), dims, str, box, es, CU_TENSOR_MAP_INTERLEAVE_NONE, sw,
      CU_TENSOR_MAP_L2_PROMOTION_L2_128B, CU_TENSOR_MAP_FLOAT_OOB_FILL_NONE);
}

}

extern "C" void kernel_launch(void* const* d_in, const int* in_sizes, int n_in, void* d_out, int out_size) {
  static EncFn enc = nullptr;
  if (!enc) {
    void* fn = nullptr;
    cudaDriverEntryPointQueryResult qr;
    cudaGetDriverEntryPoint("cuTensorMapEncodeTiled", &fn, cudaEnableDefault, &qr);
    enc = (EncFn)fn;
    cudaFuncSetAttribute(fused_kernel, cudaFuncAttributeMaxDynamicSharedMemorySize, SMEM_BYTES);
  }
  CUtensorMap tmG4, tmU4, tmG3, tmU3, tmWd;
  make_map(enc, &tmG4, d_in[8], 32, kD, kF, 32, 4, CU_TENSOR_MAP_SWIZZLE_64B);
  make_map(enc, &tmU4, d_in[9], 32, kD, kF, 32, 4, CU_TENSOR_MAP_SWIZZLE_64B);
  make_map(enc, &tmG3, d_in[8], 32, kD, kF, 32, 3, CU_TENSOR_MAP_SWIZZLE_64B);
  make_map(enc, &tmU3, d_in[9], 32, kD, kF, 32, 3, CU_TENSOR_MAP_SWIZZLE_64B);
  make_map(enc, &tmWd, d_in[10], 64, kF, kD, 32, 1, CU_TENSOR_MAP_SWIZZLE_128B);
  CUtensorMap tmU;
  {
    void* xt = nullptr;
    cudaGetSymbolAddress(&xt, g_xnT);
    cuuint64_t dims[3] = {64, 128, 128};
    cuuint64_t str[2] = {128, 16384};
    cuuint32_t box[3] = {64, 128 + U_PAD, 1};
    cuuint32_t es[3] = {1, 1, 1};
    enc(&tmU, CU_TENSOR_MAP_DATA_TYPE_BFLOAT16, 3, xt, dims, str, box, es, CU_TENSOR_MAP_INTERLEAVE_NONE, CU_TENSOR_MAP_SWIZZLE_128B,
        CU_TENSOR_MAP_L2_PROMOTION_L2_128B, CU_TENSOR_MAP_FLOAT_OOB_FILL_NONE);
  }
  CUtensorMap tmX;
  {
    cuuint64_t dims[2] = {(cuuint64_t)kD, (cuuint64_t)kL};
    cuuint64_t str[1] = {(cuuint64_t)kD * 2};
    cuuint32_t box[2] = {64, 128};
    cuuint32_t es[2] = {1, 1};
    enc(&tmX, CU_TENSOR_MAP_DATA_TYPE_BFLOAT16, 2, d_in[0], dims, str, box, es, CU_TENSOR_MAP_INTERLEAVE_NONE, CU_TENSOR_MAP_SWIZZLE_128B,
        CU_TENSOR_MAP_L2_PROMOTION_L2_128B, CU_TENSOR_MAP_FLOAT_OOB_FILL_NONE);
  }
  Params P;
  P.wg = (const __nv_bfloat16*)d_in[8];
  P.wu = (const __nv_bfloat16*)d_in[9];
  P.wd = (const __nv_bfloat16*)d_in[10];
  P.x = (const __nv_bfloat16*)d_in[0];
  P.logA = (const __nv_bfloat16*)d_in[1];
  P.Aim = (const __nv_bfloat16*)d_in[2];
  P.Cre = (const __nv_bfloat16*)d_in[3];
  P.Cim = (const __nv_bfloat16*)d_in[4];
  P.logdt = (const __nv_bfloat16*)d_in[5];
  P.Dskip = (const __nv_bfloat16*)d_in[6];
  P.out = (__nv_bfloat16*)d_out;
  fused_kernel<<<128, 512, SMEM_BYTES>>>(tmG4, tmU4, tmG3, tmU3, tmWd, tmU, tmX, P);
}
```
